```python
import torch

def _softmax(x, axis=-1):
    return torch.softmax(x, dim=axis)
def _gelu(x):
    return torch.nn.functional.gelu(x, approximate="tanh")
def _silu(x):
    return torch.nn.functional.silu(x)
def _sigmoid(x):
    return torch.sigmoid(x)
def _layernorm(x, axis=-1, eps=1e-5):
    m = x.mean(dim=axis, keepdim=True)
    v = x.var(dim=axis, keepdim=True, unbiased=False)
    return (x - m) / torch.sqrt(v + eps)
def _scatter_add(tgt, idx, src, axis=0):
    return tgt.clone().index_add_(axis, idx, src)
def _segment_sum(src, seg, n):
    out = torch.zeros((n,) + src.shape[1:], dtype=src.dtype)
    return out.index_add_(0, seg, src)
def _pad(x, pw):
    flat = tuple(v for pair in reversed(pw) for v in pair)
    return torch.nn.functional.pad(x, flat)

kernel_name = 'recurrent_scan__spectral_gfnet__dense_activation_gelu__prompt'

def setup_inputs():

    _w = (lambda a: (lambda t: t.to(torch.bfloat16) if t.is_floating_point() else t)(torch.as_tensor(a)))
    def _A_setup():
        B, S, D = 1, 2048, 512
        Df = D // 2 + 1
        return {
            "x": _w((lambda *s: torch.randn(*s, dtype=torch.bfloat16) * 0.05)(B, S, D)),
            "w_r": _w((lambda *s: torch.randn(*s, dtype=torch.bfloat16) * 3.2)(S, Df) * 0.02),
            "w_i": _w((lambda *s: torch.randn(*s, dtype=torch.bfloat16) * 3.2)(S, Df) * 0.02),
        }
    _A_in = _A_setup()

    def _B_setup():
        B, S, D, F = 1, 2048, 512, 1792
        return {
            "x": _w((lambda *s: torch.randn(*s, dtype=torch.bfloat16) * 0.05)(B, S, D)),
            "w1": _w((lambda *s: torch.randn(*s, dtype=torch.bfloat16) * 3.2)(D, F) * (D ** -0.5)),
            "b1": _w((lambda *s: torch.randn(*s, dtype=torch.bfloat16) * 3.2)(F) * 0.01),
            "w2": _w((lambda *s: torch.randn(*s, dtype=torch.bfloat16) * 0.4)(F, D) * (F ** -0.5)),
            "b2": _w((lambda *s: torch.randn(*s, dtype=torch.bfloat16) * 0.4)(D) * 0.01),
        }
    _B_in = _B_setup()

    return {
        "A_x": _A_in["x"],
        "A_w_r": _A_in["w_r"],
        "A_w_i": _A_in["w_i"],
        "B_x": _B_in["x"],
        "B_w1": _B_in["w1"],
        "B_b1": _B_in["b1"],
        "B_w2": _B_in["w2"],
        "B_b2": _B_in["b2"],
    }

def reference(A_x, A_w_r, A_w_i, B_x, B_w1, B_b1, B_w2, B_b2):
    def _A_ref(x, w_r, w_i):
        B, S, D = x.shape
        X = (lambda x, axes=(-2,-1): torch.fft.rfft2(x.float(), dim=axes))(x, axes=(-2, -1))
        W = w_r + 1j * w_i
        X = X * W
        y = (lambda x, s, axes=(-2,-1): torch.fft.irfft2(x, s=s, dim=axes).to(torch.bfloat16))(X, (S, D), axes=(-2, -1))
        return y

    def _B_ref(x, w1, b1, w2, b2):
        h = torch.einsum("bsd,df->bsf", x, w1) + b1
        h = _gelu(h)
        return torch.einsum("bsf,fd->bsd", h, w2) + b2

    x = A_x
    xn = _layernorm(x, axis=-1)
    s = _A_ref(xn, A_w_r, A_w_i)
    g = _silu(_B_ref(xn, B_w1, B_b1, B_w2, B_b2))
    return x + s * g
```

```cpp
#include <cuda_runtime.h>
#include <cuda_bf16.h>
#include <cuda_fp16.h>
#include <cuda.h>
#include <stdint.h>

#define PL 8
#define PS 200
constexpr int S_ = 2048, D_ = 512, F_ = 1792;

__device__ __align__(1024) uint32_t g_Z1[258 * 2048];
__device__ __align__(1024) uint32_t g_Z2[128 * 4096];
__device__ __align__(128) uint32_t g_WT[129 * 4096];
__device__ uint32_t g_colsum[16 * 1792];
__device__ uint32_t g_stats[2048];

__device__ __forceinline__ uint32_t smem_u32(const void* p) { return (uint32_t)__cvta_generic_to_shared(p); }
__device__ __forceinline__ float bf16r(float x) { return __bfloat162float(__float2bfloat16_rn(x)); }
__device__ __forceinline__ uint32_t pack_h2(float lo, float hi) {
    uint32_t r; asm("cvt.rn.f16x2.f32 %0, %1, %2;" : "=r"(r) : "f"(hi), "f"(lo)); return r;
}
__device__ __forceinline__ uint32_t pack_bf2(float lo, float hi) {
    uint32_t r; asm("cvt.rn.bf16x2.f32 %0, %1, %2;" : "=r"(r) : "f"(hi), "f"(lo)); return r;
}
__device__ __forceinline__ float bf_lo(uint32_t v) { return __uint_as_float(v << 16); }
__device__ __forceinline__ float bf_hi(uint32_t v) { return __uint_as_float(v & 0xffff0000u); }
__device__ __forceinline__ float rcp_a(float x) { float r; asm("rcp.approx.f32 %0, %1;" : "=f"(r) : "f"(x)); return r; }
__device__ __forceinline__ float sqrt_a(float x) { float r; asm("sqrt.approx.f32 %0, %1;" : "=f"(r) : "f"(x)); return r; }
__device__ __forceinline__ float2 cis_neg(int num, float inv_den) {
    float a = (float)num * inv_den;
    a = (a > 0.5f) ? a - 1.0f : a;
    a *= 6.283185307179586f;
    return make_float2(__cosf(a), -__sinf(a));
}
__device__ __forceinline__ float2 cmul(float2 a, float2 b) { return make_float2(a.x * b.x - a.y * b.y, a.x * b.y + a.y * b.x); }
__device__ __forceinline__ void sts32(uint32_t addr, uint32_t v) { asm volatile("st.shared.u32 [%0], %1;" ::"r"(addr), "r"(v) : "memory"); }
constexpr uint32_t NEG2 = 0x80008000u;
#define OPAQUE(x) asm volatile("" : "+r"(x))
#define OPAQUEF(x) asm volatile("" : "+f"(x))
#define FFT_BAR() asm volatile("bar.sync 1, 256;" ::: "memory")
#define WSYNC(id) asm volatile("{\n.reg .pred p;\nsetp.ne.u32 p, %0, 0;\n@p bar.sync %0, 256;\n}" ::"r"(id) : "memory")
#define FBAR(dry) asm volatile("{\n.reg .pred p;\nsetp.ne.u32 p, %0, 0;\n@p bar.sync 9, 128;\n@!p bar.sync 1, 256;\n}" ::"r"(dry) : "memory")

__device__ __forceinline__ void dft8(float2 (&v)[8]) {
    const float r = 0.70710678118654752f;
    float2 a0 = make_float2(v[0].x + v[4].x, v[0].y + v[4].y), a4 = make_float2(v[0].x - v[4].x, v[0].y - v[4].y);
    float2 a1 = make_float2(v[1].x + v[5].x, v[1].y + v[5].y), a5 = make_float2(v[1].x - v[5].x, v[1].y - v[5].y);
    float2 a2 = make_float2(v[2].x + v[6].x, v[2].y + v[6].y), a6 = make_float2(v[2].x - v[6].x, v[2].y - v[6].y);
    float2 a3 = make_float2(v[3].x + v[7].x, v[3].y + v[7].y), a7 = make_float2(v[3].x - v[7].x, v[3].y - v[7].y);
    a5 = make_float2((a5.x + a5.y) * r, (a5.y - a5.x) * r);
    a6 = make_float2(a6.y, -a6.x);
    a7 = make_float2((a7.y - a7.x) * r, -(a7.x + a7.y) * r);
    float2 b0 = make_float2(a0.x + a2.x, a0.y + a2.y), b2 = make_float2(a0.x - a2.x, a0.y - a2.y);
    float2 b1 = make_float2(a1.x + a3.x, a1.y + a3.y), b3 = make_float2(a1.y - a3.y, a3.x - a1.x);
    v[0] = make_float2(b0.x + b1.x, b0.y + b1.y); v[4] = make_float2(b0.x - b1.x, b0.y - b1.y);
    v[2] = make_float2(b2.x + b3.x, b2.y + b3.y); v[6] = make_float2(b2.x - b3.x, b2.y - b3.y);
    float2 c0 = make_float2(a4.x + a6.x, a4.y + a6.y), c2 = make_float2(a4.x - a6.x, a4.y - a6.y);
    float2 c1 = make_float2(a5.x + a7.x, a5.y + a7.y), c3 = make_float2(a5.y - a7.y, a7.x - a5.x);
    v[1] = make_float2(c0.x + c1.x, c0.y + c1.y); v[5] = make_float2(c0.x - c1.x, c0.y - c1.y);
    v[3] = make_float2(c2.x + c3.x, c2.y + c3.y); v[7] = make_float2(c2.x - c3.x, c2.y - c3.y);
}

__device__ __forceinline__ void dft32_seeds(uint32_t (&Cs)[4], uint32_t (&Ns)[4], int tid) {
    const int kk = (tid >> 2) & 31, t = tid & 3;
#pragma unroll
    for (int hz = 0; hz < 4; hz++) {
        const int n0 = 8 * hz + 2 * t;
        const float2 a = cis_neg((kk * n0) & 31, 1.0f / 32.0f), b = cis_neg((kk * (n0 + 1)) & 31, 1.0f / 32.0f);
        Cs[hz] = pack_h2(0.125f * a.x, 0.125f * b.x); Ns[hz] = pack_h2(0.125f * a.y, 0.125f * b.y);
    }
}

__device__ __forceinline__ uint4 ldcv4(const void* p) {
    uint4 v; asm volatile("ld.relaxed.gpu.global.v4.u32 {%0,%1,%2,%3}, [%4];" : "=r"(v.x), "=r"(v.y), "=r"(v.z), "=r"(v.w) : "l"(p) : "memory"); return v;
}
__device__ __forceinline__ uint2 ldcv2(const void* p) {
    uint2 v; asm volatile("ld.relaxed.gpu.global.v2.u32 {%0,%1}, [%2];" : "=r"(v.x), "=r"(v.y) : "l"(p) : "memory"); return v;
}
__device__ __forceinline__ void stg128p(void* p, uint32_t a, uint32_t b, uint32_t c, uint32_t d, int on) {
    asm volatile("{\n.reg .pred p;\nsetp.ne.s32 p, %5, 0;\n@p st.relaxed.gpu.global.v4.u32 [%0], {%1,%2,%3,%4};\n}" ::"l"(p), "r"(a), "r"(b), "r"(c), "r"(d), "r"(on) : "memory");
}
__device__ __forceinline__ void sts32p(uint32_t addr, uint32_t v, int on) {
    asm volatile("{\n.reg .pred p;\nsetp.ne.s32 p, %2, 0;\n@p st.shared.u32 [%0], %1;\n}" ::"r"(addr), "r"(v), "r"(on) : "memory");
}
__device__ __forceinline__ void ll_fetch(const uint4* s0, const uint4* s1, uint32_t dst, uint32_t dstep, uint32_t par, uint32_t wmask, int tid) {
    uint4 v[8];
    if (tid < 32) {
        for (unsigned it = 0;; it++) {
            uint32_t pr = par;
            if (tid < PL) asm volatile("ld.relaxed.gpu.global.u32 %0, [%1];" : "=r"(pr) : "l"((tid & 1 ? s1 : s0) + (512 / PL) * tid + (tid & 7)) : "memory");
            if (__all_sync(0xffffffffu, !((pr ^ par) & 1))) break;
            if (it > 1000000u) __trap();
            __nanosleep(PS);
        }
    }
    asm volatile("bar.sync 10, 128;" ::: "memory");
    for (unsigned it = 0;; it++) {
        uint32_t bad = 0;
#pragma unroll
        for (int i = 0; i < 8; i++) { v[i] = ldcv4((i & 4 ? s1 : s0) + 128 * (i & 3) + tid); bad |= (v[i].x ^ par) | ((v[i].z ^ par) & wmask); }
        if (!__any_sync(0xffffffffu, bad & 1)) break;
        if (it > 300000u) __trap();
        __nanosleep(200);
    }
#pragma unroll
    for (int i = 0; i < 8; i++)
        asm volatile("st.shared.v4.u32 [%0], {%1,%2,%3,%4};" ::"r"(dst + i * dstep), "r"(v[i].x), "r"(v[i].y), "r"(v[i].z), "r"(v[i].w) : "memory");
}

__device__ __forceinline__ float red4(const float (&s)[4], int lane) {
    const bool o1 = lane & 1, o2 = lane & 2;
    const float u0 = (o1 ? s[2] : s[0]) + __shfl_xor_sync(0xffffffffu, o1 ? s[0] : s[2], 1);
    const float u1 = (o1 ? s[3] : s[1]) + __shfl_xor_sync(0xffffffffu, o1 ? s[1] : s[3], 1);
    float v = (o2 ? u1 : u0) + __shfl_xor_sync(0xffffffffu, o2 ? u0 : u1, 2);
#pragma unroll
    for (int o = 4; o < 32; o <<= 1) v += __shfl_xor_sync(0xffffffffu, v, o);
    return v;
}
__device__ __forceinline__ void ln_stats(uint4 (&xv)[8], uint32_t* dst, uint32_t par, int lane) {
    float ml[4], m2[4];
#pragma unroll 1
    for (int i = 0; i < 4; i++) {
        const uint32_t xw[8] = {xv[0].x, xv[0].y, xv[0].z, xv[0].w, xv[1].x, xv[1].y, xv[1].z, xv[1].w};
#pragma unroll
        for (int z = 0; z < 6; z++) xv[z] = xv[z + 2];
        float f[16];
#pragma unroll
        for (int z = 0; z < 8; z++) { f[2 * z] = bf_lo(xw[z]); f[2 * z + 1] = bf_hi(xw[z]); }
        float s4[4];
#pragma unroll
        for (int z = 0; z < 4; z++) s4[z] = (f[4 * z] + f[4 * z + 1]) + (f[4 * z + 2] + f[4 * z + 3]);
        const float mean = ((s4[0] + s4[1]) + (s4[2] + s4[3])) * (1.0f / 16.0f);
#pragma unroll
        for (int z = 0; z < 4; z++) s4[z] = 0.f;
#pragma unroll
        for (int z = 0; z < 16; z++) { float d = f[z] - mean; s4[z & 3] = fmaf(d, d, s4[z & 3]); }
#pragma unroll
        for (int z = 0; z < 3; z++) { ml[z] = ml[z + 1]; m2[z] = m2[z + 1]; }
        ml[3] = mean; m2[3] = (s4[0] + s4[1]) + (s4[2] + s4[3]);
    }
    const float mean = red4(ml, lane) * (1.0f / 32.0f);
#pragma unroll
    for (int a = 0; a < 4; a++) { const float d = ml[a] - __shfl_sync(0xffffffffu, mean, (a >> 1) | ((a & 1) << 1)); m2[a] = fmaf(16.f * d, d, m2[a]); }
    const float vs = red4(m2, lane);
    const float sg = sqrt_a(bf16r(bf16r(vs * (1.0f / 512.0f)) + 1e-5f));
    if (lane < 4) asm volatile("st.relaxed.gpu.global.u32 [%0], %1;" ::"l"(dst + ((lane >> 1) | ((lane & 1) << 1))), "r"(pack_bf2(mean, sg) | (par << 31)) : "memory");
}

__device__ __forceinline__ void postC(float (&acc)[32], uint32_t buf, int on, int wid, int tid) {
    OPAQUE(tid);
    const int k2 = (tid >> 2) & 31, t = tid & 3;
    float2 om = cis_neg(k2, 1.0f / 256.0f);
#pragma unroll 1
    for (int e = 0; e < 2; e++) {
        const int rho = 8 * (t & 1) + 4 * (tid >> 7) + (t & 2) + e;
        float2 v[8];
        float2 tw = make_float2(0.5f, 0.f);
        OPAQUEF(om.x); OPAQUEF(om.y);
#pragma unroll
        for (int n1 = 0; n1 < 8; n1++) {
            float* a = acc + 4 * n1;
            v[n1] = cmul(make_float2(a[0], a[2]), tw);
            tw = cmul(tw, om);
            a[0] = a[1]; a[2] = a[3];
        }
        dft8(v);
        WSYNC(e ? 0 : wid);
        const uint32_t ad = buf + rho * 1024 + ((k2 ^ (((t >> 1) | ((t & 1) << 1)) << 3)) << 2);
#pragma unroll
        for (int k1 = 0; k1 < 8; k1++) sts32p(ad + 128 * k1, pack_bf2(v[k1].x, -v[k1].y), on);
    }
}
__device__ __forceinline__ void post13(float (&acc)[32], int is3, uint32_t buf, int wid, int tid) {
    OPAQUE(tid);
    const int j = tid >> 7, w = (tid >> 5) & 3, g = (tid >> 2) & 7, t = tid & 3;
    const int E = 2 * ((tid >> 2) & 31) + (is3 ? j : 0);
    const float2 om = cis_neg(E, 1.0f / 2048.0f), gm = cis_neg((8 * E) & 2047, 1.0f / 2048.0f);
    float2 b0 = cis_neg((2 * t * E) & 2047, 1.0f / 2048.0f);
    const uint32_t base = buf + (is3 ? 8 * w + 32 * j + g : 32 * w + 8 * j + g) * 128 + 4 * t;
    const uint32_t gs = is3 ? 64 * 128 : 16 * 128;
    OPAQUEF(b0.x); OPAQUEF(b0.y);
    WSYNC(wid);
#pragma unroll
    for (int a = 0; a < 4; a++) {
        const float2 b1 = cmul(b0, om);
#pragma unroll
        for (int G = 0; G < 2; G++) {
            const float* q = acc + 16 * G + 4 * a;
            const float2 x0 = cmul(make_float2(q[0], q[2]), b0), x1 = cmul(make_float2(q[1], q[3]), b1);
            sts32(base + G * gs + ((a ^ g) << 4), pack_h2(x0.x, x1.x));
            sts32(base + G * gs + (((4 + a) ^ g) << 4), pack_h2(x0.y, x1.y));
        }
        b0 = cmul(b0, gm);
    }
}

__device__ __forceinline__ void post2(float (&acc)[32], int u, uint32_t wt, uint32_t buf, int wid, int tid) {
    OPAQUE(tid);
    uint4 qa[2], qb[2];
#pragma unroll
    for (int z = 0; z < 2; z++) {
        asm volatile("ld.shared.v4.u32 {%0,%1,%2,%3}, [%4];" : "=r"(qa[z].x), "=r"(qa[z].y), "=r"(qa[z].z), "=r"(qa[z].w) : "r"(wt + tid * 16 + z * 4096));
        asm volatile("ld.shared.v4.u32 {%0,%1,%2,%3}, [%4];" : "=r"(qb[z].x), "=r"(qb[z].y), "=r"(qb[z].z), "=r"(qb[z].w) : "r"(wt + tid * 16 + z * 4096 + 8192));
    }
    const int k1 = (tid >> 2) & 31, g = k1 & 7, t = tid & 3;
    const float2 wu = cis_neg(u, 1.0f / 512.0f);
    float2 w64 = cis_neg(k1, 1.0f / 64.0f);
    w64.x *= 0.5f; w64.y *= 0.5f;
#pragma unroll 1
    for (int ah = 0; ah < 2; ah++) {
        const int a = 2 * (tid >> 7) + ah;
        float2 tau = cis_neg(8 * a + 2 * t + 32 * k1, 1.0f / 2048.0f);
        float2 S[2][2], Dd[2][2];
#pragma unroll
        for (int e = 0; e < 2; e++) {
            float2 R[2][2], X[2][2];
#pragma unroll
            for (int col = 0; col < 2; col++) {
                const float2 v0 = make_float2(acc[4 * col + e], acc[4 * col + 2 + e]);
                const float2 v1 = cmul(make_float2(acc[8 + 4 * col + e], acc[8 + 4 * col + 2 + e]), tau);
                X[0][col] = make_float2(v0.x + v1.x, v0.y + v1.y); X[1][col] = make_float2(v0.x - v1.x, v0.y - v1.y);
            }
            tau = cmul(tau, make_float2(0.99999529380957619f, -0.0030679567629659761f));
#pragma unroll
            for (int k0 = 0; k0 < 2; k0++) {
                const uint32_t wa = e ? qa[k0].y : qa[k0].x, wb = e ? qb[k0].y : qb[k0].x;
                const float2 P1 = cmul(X[k0][0], make_float2(bf_lo(wa), bf_hi(wa))), Q2 = cmul(X[k0][1], make_float2(bf_lo(wb), bf_hi(wb)));
                const float2 E2 = make_float2(P1.x + Q2.x, P1.y + Q2.y);
                const float2 O2 = cmul(make_float2(P1.x - Q2.x, P1.y - Q2.y), make_float2(wu.x, -wu.y));
                R[k0][0] = make_float2(E2.x - O2.y, -(E2.y + O2.x));
                R[k0][1] = make_float2(E2.x + O2.y, O2.x - E2.y);
            }
#pragma unroll
            for (int col = 0; col < 2; col++) {
                S[e][col] = make_float2(0.5f * (R[0][col].x + R[1][col].x), 0.5f * (R[0][col].y + R[1][col].y));
                Dd[e][col] = cmul(make_float2(R[0][col].x - R[1][col].x, R[0][col].y - R[1][col].y), w64);
            }
        }
        WSYNC(ah ? 0 : wid);
#pragma unroll
        for (int col = 0; col < 2; col++) {
            const uint32_t a2 = buf + k1 * 128 + 4 * t + (((col * 4 + a) ^ g) << 4);
            sts32(a2, pack_h2(S[0][col].x, S[1][col].x)); sts32(a2 + 4096, pack_h2(S[0][col].y, S[1][col].y));
            sts32(a2 + 8192, pack_h2(Dd[0][col].x, Dd[1][col].x)); sts32(a2 + 12288, pack_h2(Dd[0][col].y, Dd[1][col].y));
        }
#pragma unroll
        for (int z = 0; z < 2; z++) { qa[z].x = qa[z].z; qa[z].y = qa[z].w; qb[z].x = qb[z].z; qb[z].y = qb[z].w; }
#pragma unroll
        for (int z = 0; z < 16; z++) acc[z] = acc[16 + z];
    }
}
__device__ __forceinline__ void post4(const float (&acc)[32], int u, uint32_t par, int tid) {
    OPAQUE(tid);
    const int col = tid >> 7;
    if (col && (u & 127) == 0) return;
    const int m = col ? 256 - u : u;
    uint32_t* d = g_Z2 + ((tid >> 2) & 31) * 16384 + m * 8 + (tid & 3) * 2;
    const uint32_t sg = col ? NEG2 : 0u;
#pragma unroll
    for (int j = 0; j < 4; j++) {
        const float* q = acc + 8 * j;
        asm volatile("st.relaxed.gpu.global.v2.u32 [%0], {%1,%2};" ::"l"(d + j * 4096), "r"((pack_h2(q[0], q[1]) & ~1u) | par), "r"(pack_h2(q[4], q[5])) : "memory");
        asm volatile("st.relaxed.gpu.global.v2.u32 [%0], {%1,%2};" ::"l"(d + j * 4096 + 2048), "r"(((pack_h2(q[2], q[3]) ^ sg) & ~1u) | par), "r"(pack_h2(q[6], q[7]) ^ sg) : "memory");
    }
}

__device__ __forceinline__ void wtab_pre(uint32_t (&hx)[4], const unsigned short* __restrict__ wr, const unsigned short* __restrict__ wi, int b, int tab, int tid) {
#pragma unroll
    for (int z = 0; z < 4; z++) {
        const int i = 8 * (z >> 1) + 2 * (tid & 3) + (z & 1);
        const int ro = ((tab ? S_ - 16 * b - 16 + i : S_ - 16 * b - i) & 2047) * 257 + 256 * tab;
        hx[z] = tid < 4 ? ((uint32_t)__ldg(wr + ro) | ((uint32_t)__ldg(wi + ro) << 16)) ^ (tab ? 0u : 0x80000000u) : 0u;
    }
}
__device__ __forceinline__ void wtab(const unsigned short* sr, const unsigned short* si, const uint32_t (&hx)[4], int b, int tab, int tid) {
    const int t = tid & 3;
    const int k0f = tab ? S_ - 16 * b - 16 : 16 * b;
    uint32_t* dst = g_WT + tab * 2048 + (((k0f >> 10) * 2 + ((k0f >> 4) & 1)) * 128 + ((k0f >> 5) & 31) * 4 + t) * 4;
#pragma unroll 1
    for (int u0 = tid >> 2; u0 < 192; u0 += 96) {
        uint32_t o[3][4];
#pragma unroll
        for (int y = 0; y < 3; y++) {
            const int u = min(u0 + 32 * y, 128);
#pragma unroll
            for (int z = 0; z < 4; z++) {
                const int i = 8 * (z >> 1) + 2 * t + (z & 1);
                const int ro = tab ? (16 - i) * 257 + 256 - u : i * 257 + u;
                o[y][z] = ((uint32_t)sr[ro] | ((uint32_t)si[ro] << 16)) ^ (tab ? 0x80000000u : 0u);
                if (y == 0 && u0 == 0)
                    asm("{\n.reg .b32 h, m;\nmov.b32 h, 0x3f003f00;\nmov.b32 m, 0x80008000;\nfma.rn.bf16x2 %0, %0, h, m;\nfma.rn.bf16x2 %0, %1, h, %0;\n}" : "+r"(o[0][z]) : "r"(hx[z]));
            }
        }
#pragma unroll
        for (int y = 0; y < 3; y++) *reinterpret_cast<uint4*>(dst + min(u0 + 32 * y, 128) * 4096) = make_uint4(o[y][0], o[y][1], o[y][2], o[y][3]);
    }
}
__device__ __forceinline__ void wgmma_ss_n192(float (&d)[96], uint32_t da, uint32_t db, int sc) {
    asm volatile("{\n.reg .pred p;\n.reg .b64 a, b;\nsetp.ne.b32 p, %98, 0;\nmov.b64 a, {%96, 0x40000040};\nmov.b64 b, {%97, 0x40000040};\n"
        "wgmma.mma_async.sync.aligned.m64n192k16.f32.bf16.bf16 {%0, %1, %2, %3, %4, %5, %6, %7, %8, %9, %10, %11, %12, %13, %14, %15, %16, %17, %18, %19, %20, %21, %22, %23, %24, %25, %26, %27, %28, %29, %30, %31, %32, %33, %34, %35, %36, %37, %38, %39, %40, %41, %42, %43, %44, %45, %46, %47, %48, %49, %50, %51, %52, %53, %54, %55, %56, %57, %58, %59, %60, %61, %62, %63, %64, %65, %66, %67, %68, %69, %70, %71, %72, %73, %74, %75, %76, %77, %78, %79, %80, %81, %82, %83, %84, %85, %86, %87, %88, %89, %90, %91, %92, %93, %94, %95}, a, b, p, 1, 1, 0, 1;\n}"
        : "+f"(d[0]), "+f"(d[1]), "+f"(d[2]), "+f"(d[3]), "+f"(d[4]), "+f"(d[5]), "+f"(d[6]), "+f"(d[7]), "+f"(d[8]), "+f"(d[9]), "+f"(d[10]), "+f"(d[11]), "+f"(d[12]), "+f"(d[13]), "+f"(d[14]), "+f"(d[15]), "+f"(d[16]), "+f"(d[17]), "+f"(d[18]), "+f"(d[19]), "+f"(d[20]), "+f"(d[21]), "+f"(d[22]), "+f"(d[23]), "+f"(d[24]), "+f"(d[25]), "+f"(d[26]), "+f"(d[27]), "+f"(d[28]), "+f"(d[29]), "+f"(d[30]), "+f"(d[31]), "+f"(d[32]), "+f"(d[33]), "+f"(d[34]), "+f"(d[35]), "+f"(d[36]), "+f"(d[37]), "+f"(d[38]), "+f"(d[39]), "+f"(d[40]), "+f"(d[41]), "+f"(d[42]), "+f"(d[43]), "+f"(d[44]), "+f"(d[45]), "+f"(d[46]), "+f"(d[47]), "+f"(d[48]), "+f"(d[49]), "+f"(d[50]), "+f"(d[51]), "+f"(d[52]), "+f"(d[53]), "+f"(d[54]), "+f"(d[55]), "+f"(d[56]), "+f"(d[57]), "+f"(d[58]), "+f"(d[59]), "+f"(d[60]), "+f"(d[61]), "+f"(d[62]), "+f"(d[63]), "+f"(d[64]), "+f"(d[65]), "+f"(d[66]), "+f"(d[67]), "+f"(d[68]), "+f"(d[69]), "+f"(d[70]), "+f"(d[71]), "+f"(d[72]), "+f"(d[73]), "+f"(d[74]), "+f"(d[75]), "+f"(d[76]), "+f"(d[77]), "+f"(d[78]), "+f"(d[79]), "+f"(d[80]), "+f"(d[81]), "+f"(d[82]), "+f"(d[83]), "+f"(d[84]), "+f"(d[85]), "+f"(d[86]), "+f"(d[87]), "+f"(d[88]), "+f"(d[89]), "+f"(d[90]), "+f"(d[91]), "+f"(d[92]), "+f"(d[93]), "+f"(d[94]), "+f"(d[95]) : "r"(da), "r"(db), "r"(sc));
}
__device__ __forceinline__ void wgmma_ss_n32(float (&d)[16], uint32_t da, uint32_t db, int sc) {
    asm volatile("{\n.reg .pred p;\n.reg .b64 a, b;\nsetp.ne.b32 p, %18, 0;\nmov.b64 a, {%16, 0x40000040};\nmov.b64 b, {%17, 0x40000040};\n"
        "wgmma.mma_async.sync.aligned.m64n32k16.f32.bf16.bf16 {%0, %1, %2, %3, %4, %5, %6, %7, %8, %9, %10, %11, %12, %13, %14, %15}, a, b, p, 1, 1, 0, 1;\n}"
        : "+f"(d[0]), "+f"(d[1]), "+f"(d[2]), "+f"(d[3]), "+f"(d[4]), "+f"(d[5]), "+f"(d[6]), "+f"(d[7]), "+f"(d[8]), "+f"(d[9]), "+f"(d[10]), "+f"(d[11]), "+f"(d[12]), "+f"(d[13]), "+f"(d[14]), "+f"(d[15]) : "r"(da), "r"(db), "r"(sc));
}
__device__ __forceinline__ void wgmma_rs_n128(float (&d)[64], uint32_t a0, uint32_t a1, uint32_t a2, uint32_t a3, uint32_t db, int sc) {
    asm volatile("{\n.reg .pred p;\n.reg .b64 b;\nmov.b64 b, {%68, 0x40000040};\nsetp.ne.b32 p, %69, 0;\n"
        "wgmma.mma_async.sync.aligned.m64n128k16.f32.bf16.bf16 {%0, %1, %2, %3, %4, %5, %6, %7, %8, %9, %10, %11, %12, %13, %14, %15, %16, %17, %18, %19, %20, %21, %22, %23, %24, %25, %26, %27, %28, %29, %30, %31, %32, %33, %34, %35, %36, %37, %38, %39, %40, %41, %42, %43, %44, %45, %46, %47, %48, %49, %50, %51, %52, %53, %54, %55, %56, %57, %58, %59, %60, %61, %62, %63}, {%64, %65, %66, %67}, b, p, 1, 1, 1;\n}"
        : "+f"(d[0]), "+f"(d[1]), "+f"(d[2]), "+f"(d[3]), "+f"(d[4]), "+f"(d[5]), "+f"(d[6]), "+f"(d[7]), "+f"(d[8]), "+f"(d[9]), "+f"(d[10]), "+f"(d[11]), "+f"(d[12]), "+f"(d[13]), "+f"(d[14]), "+f"(d[15]), "+f"(d[16]), "+f"(d[17]), "+f"(d[18]), "+f"(d[19]), "+f"(d[20]), "+f"(d[21]), "+f"(d[22]), "+f"(d[23]), "+f"(d[24]), "+f"(d[25]), "+f"(d[26]), "+f"(d[27]), "+f"(d[28]), "+f"(d[29]), "+f"(d[30]), "+f"(d[31]), "+f"(d[32]), "+f"(d[33]), "+f"(d[34]), "+f"(d[35]), "+f"(d[36]), "+f"(d[37]), "+f"(d[38]), "+f"(d[39]), "+f"(d[40]), "+f"(d[41]), "+f"(d[42]), "+f"(d[43]), "+f"(d[44]), "+f"(d[45]), "+f"(d[46]), "+f"(d[47]), "+f"(d[48]), "+f"(d[49]), "+f"(d[50]), "+f"(d[51]), "+f"(d[52]), "+f"(d[53]), "+f"(d[54]), "+f"(d[55]), "+f"(d[56]), "+f"(d[57]), "+f"(d[58]), "+f"(d[59]), "+f"(d[60]), "+f"(d[61]), "+f"(d[62]), "+f"(d[63]) : "r"(a0), "r"(a1), "r"(a2), "r"(a3), "r"(db), "r"(sc));
}
__device__ __forceinline__ void wgmma_rs_n32(float (&d)[16], uint32_t a0, uint32_t a1, uint32_t a2, uint32_t a3, uint64_t db, int sc) {
    asm volatile("{\n.reg .pred p;\nsetp.ne.b32 p, %21, 0;\n"
        "wgmma.mma_async.sync.aligned.m64n32k16.f32.bf16.bf16 {%0, %1, %2, %3, %4, %5, %6, %7, %8, %9, %10, %11, %12, %13, %14, %15}, {%16, %17, %18, %19}, %20, p, 1, 1, 1;\n}"
        : "+f"(d[0]), "+f"(d[1]), "+f"(d[2]), "+f"(d[3]), "+f"(d[4]), "+f"(d[5]), "+f"(d[6]), "+f"(d[7]), "+f"(d[8]), "+f"(d[9]), "+f"(d[10]), "+f"(d[11]), "+f"(d[12]), "+f"(d[13]), "+f"(d[14]), "+f"(d[15]) : "r"(a0), "r"(a1), "r"(a2), "r"(a3), "l"(db), "r"(sc));
}
__device__ __forceinline__ void wgmma_rs_n192(float (&d)[96], uint32_t a0, uint32_t a1, uint32_t a2, uint32_t a3, uint64_t db, int sc) {
    asm volatile("{\n.reg .pred p;\nsetp.ne.b32 p, %101, 0;\n"
        "wgmma.mma_async.sync.aligned.m64n192k16.f32.bf16.bf16 {%0, %1, %2, %3, %4, %5, %6, %7, %8, %9, %10, %11, %12, %13, %14, %15, %16, %17, %18, %19, %20, %21, %22, %23, %24, %25, %26, %27, %28, %29, %30, %31, %32, %33, %34, %35, %36, %37, %38, %39, %40, %41, %42, %43, %44, %45, %46, %47, %48, %49, %50, %51, %52, %53, %54, %55, %56, %57, %58, %59, %60, %61, %62, %63, %64, %65, %66, %67, %68, %69, %70, %71, %72, %73, %74, %75, %76, %77, %78, %79, %80, %81, %82, %83, %84, %85, %86, %87, %88, %89, %90, %91, %92, %93, %94, %95}, {%96, %97, %98, %99}, %100, p, 1, 1, 1;\n}"
        : "+f"(d[0]), "+f"(d[1]), "+f"(d[2]), "+f"(d[3]), "+f"(d[4]), "+f"(d[5]), "+f"(d[6]), "+f"(d[7]), "+f"(d[8]), "+f"(d[9]), "+f"(d[10]), "+f"(d[11]), "+f"(d[12]), "+f"(d[13]), "+f"(d[14]), "+f"(d[15]), "+f"(d[16]), "+f"(d[17]), "+f"(d[18]), "+f"(d[19]), "+f"(d[20]), "+f"(d[21]), "+f"(d[22]), "+f"(d[23]), "+f"(d[24]), "+f"(d[25]), "+f"(d[26]), "+f"(d[27]), "+f"(d[28]), "+f"(d[29]), "+f"(d[30]), "+f"(d[31]), "+f"(d[32]), "+f"(d[33]), "+f"(d[34]), "+f"(d[35]), "+f"(d[36]), "+f"(d[37]), "+f"(d[38]), "+f"(d[39]), "+f"(d[40]), "+f"(d[41]), "+f"(d[42]), "+f"(d[43]), "+f"(d[44]), "+f"(d[45]), "+f"(d[46]), "+f"(d[47]), "+f"(d[48]), "+f"(d[49]), "+f"(d[50]), "+f"(d[51]), "+f"(d[52]), "+f"(d[53]), "+f"(d[54]), "+f"(d[55]), "+f"(d[56]), "+f"(d[57]), "+f"(d[58]), "+f"(d[59]), "+f"(d[60]), "+f"(d[61]), "+f"(d[62]), "+f"(d[63]), "+f"(d[64]), "+f"(d[65]), "+f"(d[66]), "+f"(d[67]), "+f"(d[68]), "+f"(d[69]), "+f"(d[70]), "+f"(d[71]), "+f"(d[72]), "+f"(d[73]), "+f"(d[74]), "+f"(d[75]), "+f"(d[76]), "+f"(d[77]), "+f"(d[78]), "+f"(d[79]), "+f"(d[80]), "+f"(d[81]), "+f"(d[82]), "+f"(d[83]), "+f"(d[84]), "+f"(d[85]), "+f"(d[86]), "+f"(d[87]), "+f"(d[88]), "+f"(d[89]), "+f"(d[90]), "+f"(d[91]), "+f"(d[92]), "+f"(d[93]), "+f"(d[94]), "+f"(d[95]) : "r"(a0), "r"(a1), "r"(a2), "r"(a3), "l"(db), "r"(sc));
}
__device__ __forceinline__ void wgmma_fftN(float (&d)[32], uint32_t a0, uint32_t a1, uint32_t a2, uint32_t a3, uint32_t db) {
    asm volatile("{\n.reg .pred p;\n.reg .b64 b;\nmov.b64 b, {%36, 0x40000040};\nsetp.ne.b32 p, 1, 0;\n"
        "wgmma.mma_async.sync.aligned.m64n64k16.f32.f16.f16 {%0, %1, %2, %3, %4, %5, %6, %7, %8, %9, %10, %11, %12, %13, %14, %15, %16, %17, %18, %19, %20, %21, %22, %23, %24, %25, %26, %27, %28, %29, %30, %31}, {%32, %33, %34, %35}, b, p, 1, 1, 1;\n}"
        : "+f"(d[0]), "+f"(d[1]), "+f"(d[2]), "+f"(d[3]), "+f"(d[4]), "+f"(d[5]), "+f"(d[6]), "+f"(d[7]), "+f"(d[8]), "+f"(d[9]), "+f"(d[10]), "+f"(d[11]), "+f"(d[12]), "+f"(d[13]), "+f"(d[14]), "+f"(d[15]), "+f"(d[16]), "+f"(d[17]), "+f"(d[18]), "+f"(d[19]), "+f"(d[20]), "+f"(d[21]), "+f"(d[22]), "+f"(d[23]), "+f"(d[24]), "+f"(d[25]), "+f"(d[26]), "+f"(d[27]), "+f"(d[28]), "+f"(d[29]), "+f"(d[30]), "+f"(d[31]) : "r"(a0), "r"(a1), "r"(a2), "r"(a3), "r"(db));
}
__device__ __forceinline__ void wgmma_fftK(float (&d)[32], uint32_t a0, uint32_t a1, uint32_t a2, uint32_t a3, uint32_t db) {
    asm volatile("{\n.reg .pred p;\n.reg .b64 b;\nmov.b64 b, {%36, 0x40000040};\nsetp.ne.b32 p, 1, 0;\n"
        "wgmma.mma_async.sync.aligned.m64n64k16.f32.f16.f16 {%0, %1, %2, %3, %4, %5, %6, %7, %8, %9, %10, %11, %12, %13, %14, %15, %16, %17, %18, %19, %20, %21, %22, %23, %24, %25, %26, %27, %28, %29, %30, %31}, {%32, %33, %34, %35}, b, p, 1, 1, 0;\n}"
        : "+f"(d[0]), "+f"(d[1]), "+f"(d[2]), "+f"(d[3]), "+f"(d[4]), "+f"(d[5]), "+f"(d[6]), "+f"(d[7]), "+f"(d[8]), "+f"(d[9]), "+f"(d[10]), "+f"(d[11]), "+f"(d[12]), "+f"(d[13]), "+f"(d[14]), "+f"(d[15]), "+f"(d[16]), "+f"(d[17]), "+f"(d[18]), "+f"(d[19]), "+f"(d[20]), "+f"(d[21]), "+f"(d[22]), "+f"(d[23]), "+f"(d[24]), "+f"(d[25]), "+f"(d[26]), "+f"(d[27]), "+f"(d[28]), "+f"(d[29]), "+f"(d[30]), "+f"(d[31]) : "r"(a0), "r"(a1), "r"(a2), "r"(a3), "r"(db));
}
__device__ __forceinline__ void wgmma_fftNz(float (&d)[32], uint32_t a0, uint32_t a1, uint32_t a2, uint32_t a3, uint32_t db) {
    asm volatile("{\n.reg .pred p;\n.reg .b64 b;\nmov.b64 b, {%36, 0x40000040};\nsetp.ne.b32 p, 0, 0;\n"
        "wgmma.mma_async.sync.aligned.m64n64k16.f32.f16.f16 {%0, %1, %2, %3, %4, %5, %6, %7, %8, %9, %10, %11, %12, %13, %14, %15, %16, %17, %18, %19, %20, %21, %22, %23, %24, %25, %26, %27, %28, %29, %30, %31}, {%32, %33, %34, %35}, b, p, 1, 1, 1;\n}"
        : "=f"(d[0]), "=f"(d[1]), "=f"(d[2]), "=f"(d[3]), "=f"(d[4]), "=f"(d[5]), "=f"(d[6]), "=f"(d[7]), "=f"(d[8]), "=f"(d[9]), "=f"(d[10]), "=f"(d[11]), "=f"(d[12]), "=f"(d[13]), "=f"(d[14]), "=f"(d[15]), "=f"(d[16]), "=f"(d[17]), "=f"(d[18]), "=f"(d[19]), "=f"(d[20]), "=f"(d[21]), "=f"(d[22]), "=f"(d[23]), "=f"(d[24]), "=f"(d[25]), "=f"(d[26]), "=f"(d[27]), "=f"(d[28]), "=f"(d[29]), "=f"(d[30]), "=f"(d[31]) : "r"(a0), "r"(a1), "r"(a2), "r"(a3), "r"(db));
}
__device__ __forceinline__ void wgmma_fftKz(float (&d)[32], uint32_t a0, uint32_t a1, uint32_t a2, uint32_t a3, uint32_t db) {
    asm volatile("{\n.reg .pred p;\n.reg .b64 b;\nmov.b64 b, {%36, 0x40000040};\nsetp.ne.b32 p, 0, 0;\n"
        "wgmma.mma_async.sync.aligned.m64n64k16.f32.f16.f16 {%0, %1, %2, %3, %4, %5, %6, %7, %8, %9, %10, %11, %12, %13, %14, %15, %16, %17, %18, %19, %20, %21, %22, %23, %24, %25, %26, %27, %28, %29, %30, %31}, {%32, %33, %34, %35}, b, p, 1, 1, 0;\n}"
        : "=f"(d[0]), "=f"(d[1]), "=f"(d[2]), "=f"(d[3]), "=f"(d[4]), "=f"(d[5]), "=f"(d[6]), "=f"(d[7]), "=f"(d[8]), "=f"(d[9]), "=f"(d[10]), "=f"(d[11]), "=f"(d[12]), "=f"(d[13]), "=f"(d[14]), "=f"(d[15]), "=f"(d[16]), "=f"(d[17]), "=f"(d[18]), "=f"(d[19]), "=f"(d[20]), "=f"(d[21]), "=f"(d[22]), "=f"(d[23]), "=f"(d[24]), "=f"(d[25]), "=f"(d[26]), "=f"(d[27]), "=f"(d[28]), "=f"(d[29]), "=f"(d[30]), "=f"(d[31]) : "r"(a0), "r"(a1), "r"(a2), "r"(a3), "r"(db));
}
__device__ __forceinline__ void wgmma_dft(float (&d)[64], uint32_t a0, uint32_t a1, uint32_t a2, uint32_t a3, uint32_t db, int sc) {
    asm volatile("{\n.reg .pred p;\n.reg .b64 b;\nmov.b64 b, {%68, 0x40000040};\nsetp.ne.b32 p, %69, 0;\n"
        "wgmma.mma_async.sync.aligned.m64n128k16.f32.bf16.bf16 {%0, %1, %2, %3, %4, %5, %6, %7, %8, %9, %10, %11, %12, %13, %14, %15, %16, %17, %18, %19, %20, %21, %22, %23, %24, %25, %26, %27, %28, %29, %30, %31, %32, %33, %34, %35, %36, %37, %38, %39, %40, %41, %42, %43, %44, %45, %46, %47, %48, %49, %50, %51, %52, %53, %54, %55, %56, %57, %58, %59, %60, %61, %62, %63}, {%64, %65, %66, %67}, b, p, 1, 1, 0;\n}"
        : "+f"(d[0]), "+f"(d[1]), "+f"(d[2]), "+f"(d[3]), "+f"(d[4]), "+f"(d[5]), "+f"(d[6]), "+f"(d[7]), "+f"(d[8]), "+f"(d[9]), "+f"(d[10]), "+f"(d[11]), "+f"(d[12]), "+f"(d[13]), "+f"(d[14]), "+f"(d[15]), "+f"(d[16]), "+f"(d[17]), "+f"(d[18]), "+f"(d[19]), "+f"(d[20]), "+f"(d[21]), "+f"(d[22]), "+f"(d[23]), "+f"(d[24]), "+f"(d[25]), "+f"(d[26]), "+f"(d[27]), "+f"(d[28]), "+f"(d[29]), "+f"(d[30]), "+f"(d[31]), "+f"(d[32]), "+f"(d[33]), "+f"(d[34]), "+f"(d[35]), "+f"(d[36]), "+f"(d[37]), "+f"(d[38]), "+f"(d[39]), "+f"(d[40]), "+f"(d[41]), "+f"(d[42]), "+f"(d[43]), "+f"(d[44]), "+f"(d[45]), "+f"(d[46]), "+f"(d[47]), "+f"(d[48]), "+f"(d[49]), "+f"(d[50]), "+f"(d[51]), "+f"(d[52]), "+f"(d[53]), "+f"(d[54]), "+f"(d[55]), "+f"(d[56]), "+f"(d[57]), "+f"(d[58]), "+f"(d[59]), "+f"(d[60]), "+f"(d[61]), "+f"(d[62]), "+f"(d[63]) : "r"(a0), "r"(a1), "r"(a2), "r"(a3), "r"(db), "r"(sc));
}
__device__ uint4    g_part[128 * 8192];
__device__ unsigned g_epoch, g_cntW;
#define TS(i)

constexpr int NTHREADS = 512;
#define FD 1
#define PACE 200
#define PACE2 900
constexpr int OFF_W1 = 131072, W1SLOT = 32768;
constexpr int OFF_FFT = 0, OFF_WST = 16384, OFF_W2 = 34816, OFF_H = 149504, OFF_RECV = OFF_H, OFF_CS = 229376;
constexpr int OFF_OWN = 215040, OFF_G = OFF_W2 + 98304;
constexpr int OFF_BX = 34816;
constexpr int OFF_ST = OFF_CS, OFF_RS = OFF_ST + 512, OFF_BAR = OFF_RS + 1024;
constexpr int NBAR = 33;
constexpr int OFF_CNT = OFF_BAR + NBAR * 8, OFF_TW = OFF_CNT + 32 * 4, OFF_EP = OFF_TW + 128;
constexpr int SMEM_BYTES = OFF_EP + 16;
static_assert(SMEM_BYTES <= 232448, "smem");

struct Maps { CUtensorMap m[3]; };

__device__ __forceinline__ void mbar_init(uint32_t bar, int cnt) { asm volatile("mbarrier.init.shared::cta.b64 [%0], %1;" ::"r"(bar), "r"(cnt)); }
__device__ __forceinline__ void mbar_expect_tx(uint32_t bar, uint32_t bytes) { asm volatile("mbarrier.arrive.expect_tx.shared::cta.b64 _, [%0], %1;" ::"r"(bar), "r"(bytes) : "memory"); }
__device__ __forceinline__ void mbar_wait(uint32_t bar, uint32_t parity) {
    asm volatile("{\n.reg .pred p;\n.reg .u32 n;\nmov.u32 n, 0;\n"
                 "W_%=:\nmbarrier.try_wait.parity.shared::cta.b64 p, [%0], %1;\n@p bra D_%=;\n"
                 "add.u32 n, n, 1;\nsetp.lt.u32 p, n, 300000;\n@p bra W_%=;\ntrap;\nD_%=:\n}" ::"r"(bar), "r"(parity) : "memory");
}
__device__ __forceinline__ void wait_cnt(const unsigned* p, unsigned target) {
    asm volatile("{\n.reg .pred p;\n.reg .u32 n, v;\nmov.u32 n, 0;\n"
                 "W_%=:\nld.acquire.gpu.global.u32 v, [%0];\nsub.u32 v, v, %1;\nsetp.ge.s32 p, v, 0;\n@p bra D_%=;\n"
                 "nanosleep.u32 100;\nadd.u32 n, n, 1;\nsetp.lt.u32 p, n, 1000000;\n@p bra W_%=;\ntrap;\n"
                 "D_%=:\n}" ::"l"(p), "r"(target) : "memory");
}
__device__ __forceinline__ void sig_cnt(unsigned* p) {
    asm volatile("fence.acq_rel.gpu;\nred.relaxed.gpu.global.add.u32 [%0], 1;" ::"l"(p) : "memory");
}
__device__ __forceinline__ void tma3(uint32_t dst, const CUtensorMap* tm, int c0, int c1, int c2, uint32_t bar) {
    asm volatile("cp.async.bulk.tensor.3d.shared::cluster.global.mbarrier::complete_tx::bytes [%0], [%1, {%3,%4,%5}], [%2];"
                 ::"r"(dst), "l"(tm), "r"(bar), "r"(c0), "r"(c1), "r"(c2) : "memory");
}
__device__ __forceinline__ void tma_x(uint32_t sb, const CUtensorMap* tm, int k, int r, uint32_t bar) {
    asm volatile("cp.async.bulk.tensor.4d.shared::cluster.global.mbarrier::complete_tx::bytes [%0], [%1, {%3,%4,%4,%5}], [%2];"
                 ::"r"(sb + k * 16384), "l"(tm), "r"(bar + 8 * k), "r"(64 * k), "r"(0), "r"(2 * r) : "memory");
}
__device__ __forceinline__ void issue_w(uint32_t sb, const Maps* maps, int ev, int f) {
    const uint32_t bar = sb + OFF_BAR + 8 * ev;
    if (ev < 8) tma3(sb + OFF_W1 + (ev % 3) * W1SLOT, &maps->m[1], 0, ev * 64, (7 * f) >> 1, bar);
    else tma3(sb + OFF_W2 + (ev & 1) * 57344, &maps->m[2], 0, 224 * f, 2 * (ev & 3), bar);
}
__device__ __forceinline__ void release(uint32_t sb, const Maps* maps, int ev, int f) {
    unsigned o1;
    asm volatile("atom.relaxed.cta.shared::cta.add.u32 %0, [%1], 1;" : "=r"(o1) : "r"(sb + OFF_CNT + 4 * ev) : "memory");
    if (o1 == 1) {
        if (ev == 9) { mbar_wait(sb + OFF_BAR + 8 * 24, 0); issue_w(sb, maps, 8, f); }
        issue_w(sb, maps, ev, f);
    }
}
__device__ __forceinline__ void fetch_parts(uint32_t sb, const uint4* gp, int bk, int f, int lane) {
    const uint32_t bar = sb + OFF_BAR + 8 * (28 + bk);
    if (lane == 0) mbar_expect_tx(bar, 28672);
    __syncwarp();
    if (lane < 8 && lane != f) asm volatile("cp.async.bulk.shared::cluster.global.mbarrier::complete_tx::bytes [%0], [%1], 4096, [%2];"
                               ::"r"(sb + (bk < 2 ? OFF_RECV : OFF_W2) + (bk & 1) * 32768 + lane * 4096), "l"(gp + lane * 1024 + bk * 256), "r"(bar) : "memory");
    __syncwarp();
}

__device__ __forceinline__ uint32_t mkdlo(uint32_t addr, uint32_t lbo) { return ((addr & 0x3FFFF) >> 4) | ((lbo >> 4) << 16); }
__device__ __forceinline__ uint64_t mkdesc(uint32_t addr, uint32_t lbo, uint32_t sbo, uint32_t swz) {
    return (uint64_t)((addr & 0x3FFFF) >> 4) | ((uint64_t)(lbo >> 4) << 16) | ((uint64_t)(sbo >> 4) << 32) | ((uint64_t)swz << 62);
}
#define WG_FENCE() asm volatile("wgmma.fence.sync.aligned;" ::: "memory")
#define WG_COMMIT() asm volatile("wgmma.commit_group.sync.aligned;" ::: "memory")
#define WG_WAIT(n) asm volatile("wgmma.wait_group.sync.aligned %0;" ::"n"(n) : "memory")
template <int N> __device__ __forceinline__ void fence_regs(float (&d)[N]) {
#pragma unroll
    for (int i = 0; i < N; i++) asm volatile("" : "+f"(d[i])::"memory");
}
__device__ __forceinline__ float gelu_h(float xh) {
    float u = xh * fmaf(xh * xh, 0.28541926509040100f, 1.5957691216057308f);
    float t; asm("tanh.approx.f32 %0, %1;" : "=f"(t) : "f"(u));
    return fmaf(xh, t, xh);
}
__device__ __forceinline__ void ship_out(const float (&a)[64], uint4* dst, uint32_t loc, uint32_t par) {
#pragma unroll
    for (int i = 0; i < 8; i++) {
        const float* q = a + 32 * (i >> 2) + 16 * (i & 1) + 2 * ((i >> 1) & 1);
        asm volatile("{\n.reg .pred p;\nsetp.eq.u32 p, %5, 0;\n@p st.relaxed.gpu.global.v4.u32 [%0], {%1,%2,%3,%4};\n@!p st.shared.v4.u32 [%6], {%1,%2,%3,%4};\n}"
                     ::"l"(dst + i * 32), "r"((pack_bf2(q[0], q[1]) & ~1u) | par), "r"(pack_bf2(q[4], q[5])), "r"(pack_bf2(q[8], q[9])), "r"(pack_bf2(q[12], q[13])), "r"(loc), "r"(loc + i * 512) : "memory");
    }
}

template <bool NMAJOR_DYN>
__device__ __forceinline__ void dft32_stage(float (&acc)[32], const uint32_t (&C)[4], const uint32_t (&N)[4], uint32_t bufw, bool nmajor) {
    const uint32_t dB = mkdlo(bufw, 16);
    uint32_t M[4];
#pragma unroll
    for (int z = 0; z < 4; z++) M[z] = N[z] ^ NEG2;
    if (NMAJOR_DYN && nmajor) {
        WG_FENCE();
        wgmma_fftNz(acc, C[0], N[0], C[1], N[1], dB); wgmma_fftN(acc, C[2], N[2], C[3], N[3], dB + 128);
        wgmma_fftN(acc, M[0], C[0], M[1], C[1], dB + 256); wgmma_fftN(acc, M[2], C[2], M[3], C[3], dB + 384);
        WG_COMMIT();
        WG_WAIT(0);
        fence_regs(acc);
    } else {
        WG_FENCE();
        wgmma_fftKz(acc, C[0], N[0], C[1], N[1], dB); wgmma_fftK(acc, C[2], N[2], C[3], N[3], dB + 2);
        wgmma_fftK(acc, M[0], C[0], M[1], C[1], dB + 4); wgmma_fftK(acc, M[2], C[2], M[3], C[3], dB + 6);
        WG_COMMIT();
        WG_WAIT(0);
        fence_regs(acc);
    }
}

__device__ __forceinline__ void load_x(uint4 (&xq)[2], const __nv_bfloat16* x, int rowb, int tid) {
#pragma unroll
    for (int i = 0; i < 2; i++) xq[i] = __ldg(reinterpret_cast<const uint4*>(x + (size_t)(rowb + 2 * (8 * i + (tid >> 6))) * D_) + (tid & 63));
}
template <int V>
__device__ __forceinline__ void combine(uint32_t sb, const uint4 (&xq)[2], __nv_bfloat16* out, int rowb, int tid) {
    asm volatile("bar.sync 11, 512;" ::: "memory");
#pragma unroll
    for (int i = 0; i < 2; i++) {
        const int ch = i * 512 + tid, rho = ch >> 6, cw = ch & 63;
        uint4 sv, gv;
        const uint4 xv = xq[i];
        asm volatile("ld.shared.v4.u32 {%0,%1,%2,%3}, [%4];" : "=r"(sv.x), "=r"(sv.y), "=r"(sv.z), "=r"(sv.w) : "r"(sb + OFF_FFT + rho * 1024 + ((cw ^ ((((rho >> 1) & 1) | ((rho >> 2) & 2)) << 1)) << 4)));
        asm volatile("ld.shared.v4.u32 {%0,%1,%2,%3}, [%4];" : "=r"(gv.x), "=r"(gv.y), "=r"(gv.z), "=r"(gv.w) : "r"(sb + OFF_G + ch * 16));
        uint32_t o[4];
#pragma unroll
        for (int z = 0; z < 4; z++) {
            const uint32_t a = (&sv.x)[z], g2 = (&gv.x)[z], c = (&xv.x)[z];
            o[z] = pack_bf2(fmaf(bf_lo(a), bf_lo(g2), bf_lo(c)), fmaf(bf_hi(a), bf_hi(g2), bf_hi(c)));
        }
        if (V) asm volatile("st.global.v4.b32 [%0], {%1,%2,%3,%4};" ::"l"(reinterpret_cast<uint4*>(out + (size_t)(rowb + 2 * rho) * D_) + cw), "r"(o[0]), "r"(o[1]), "r"(o[2]), "r"(o[3]) : "memory");
        else asm volatile("st.global.v4.u32 [%0], {%1,%2,%3,%4};" ::"l"(reinterpret_cast<uint4*>(out + (size_t)(rowb + 2 * rho) * D_) + cw), "r"(o[0]), "r"(o[1]), "r"(o[2]), "r"(o[3]) : "memory");
    }
}

__global__ void __launch_bounds__(NTHREADS, 1)
fused_kernel(const __nv_bfloat16* __restrict__ x, const __nv_bfloat16* __restrict__ wr, const __nv_bfloat16* __restrict__ wi,
             const __nv_bfloat16* __restrict__ w1, const __nv_bfloat16* __restrict__ b1, const __nv_bfloat16* __restrict__ w2,
             const __nv_bfloat16* __restrict__ b2, __nv_bfloat16* __restrict__ out, const __grid_constant__ Maps maps) {
    extern __shared__ __align__(1024) unsigned char sm[];
    const uint32_t sb = smem_u32(sm);
    const int tid = threadIdx.x, warp = tid >> 5, lane = tid & 31;
    const int bid = blockIdx.x;
    const bool extra = bid >= 128;
    const int f = (bid >> 4) & 7, r = bid & 15;
    const uint32_t bFULL = sb + OFF_BAR, bXF = bFULL + 12 * 8, bFF = bXF + 8, bX = bFF + 8, bT = bX + 8, bXK = bT + 8, bD = bXK + 64, bC0 = bD + 8, bC2 = bC0 + 8, bR = bC2 + 8, bG = bR + 8, bC5 = bG + 32;

    if (tid == 0) TS(0);
    if (lane == 0) {
        mbar_init(bFULL + 8 * warp, warp < 12 || warp == 13 ? 1 : warp == 14 ? 1 : warp == 12 ? 256 : 128);
        if (warp == 0) mbar_init(bC5, 8);
        mbar_init(bXK + 8 * warp, warp < 8 || warp >= 12 ? 1 : warp == 8 ? 4 : warp == 11 ? 128 : warp == 10 ? 12 : 8);
        if (warp < 12) mbar_expect_tx(bFULL + 8 * warp, warp < 8 ? W1SLOT : 57344);
        reinterpret_cast<unsigned*>(sm + OFF_CNT)[warp] = 0;
        reinterpret_cast<unsigned*>(sm + OFF_CNT)[16 + warp] = 0;
        asm volatile("fence.mbarrier_init.release.cluster;" ::: "memory");
        if (warp < 8 && !extra) {
            mbar_expect_tx(bXK + 8 * warp, 16384);
            if (warp == 0) { tma_x(sb, &maps.m[0], 0, r, bXK); issue_w(sb, &maps, 0, f); }
        }
    }
    __syncthreads();
    if (lane == 0 && !extra && (warp == 1 || warp == 2)) {
        const unsigned t0 = clock();
        while (clock() - t0 < (unsigned)(warp == 1 ? PACE : PACE2)) {}
        tma_x(sb, &maps.m[0], warp, r, bXK);
        issue_w(sb, &maps, warp, f);
    }
    __syncwarp();
    if (tid == 0) TS(26);
    const int n2r = 2 * r + (f >> 2), jb = (f & 1) * 32 + 16 * ((f >> 1) & 1);
    const int rowb = 64 * n2r + 32 * ((f >> 1) & 1) + (f & 1);
    if (warp >= 8) {
        const int ft = tid - 256;
        unsigned ep1 = 0, par = 0;
        const int wgi = __shfl_sync(0xffffffffu, ft >> 7, 0);
        if (extra) {
            asm volatile("setmaxnreg.dec.sync.aligned.u32 104;");
            if (ft == 128) *reinterpret_cast<volatile unsigned*>(sm + OFF_EP) = *(volatile unsigned*)&g_epoch + 1;
            FFT_BAR();
            ep1 = *reinterpret_cast<volatile unsigned*>(sm + OFF_EP); par = ep1 & 1;
        } else if (wgi) {
            asm volatile("setmaxnreg.dec.sync.aligned.u32 104;");
            const int i = ft - 128;
            uint4 xv[8];
            {
                const uint4* src = reinterpret_cast<const uint4*>(x + (size_t)(16 * bid + 4 * (warp - 12)) * D_) + lane;
#pragma unroll
                for (int z = 0; z < 8; z++) xv[z] = __ldg(src + 32 * z);
            }
            if (lane == 0) ep1 = *(volatile unsigned*)&g_epoch;
            ep1 = __shfl_sync(0xffffffffu, ep1, 0) + 1; par = ep1 & 1;
            if (i == 0) *reinterpret_cast<volatile unsigned*>(sm + OFF_EP) = ep1;
            ln_stats(xv, g_stats + 16 * bid + 4 * (warp - 12), par, lane);
            if (i == 0) TS(7);
            uint4 ev_[8];
            {
                const int l2 = lane < 28 ? lane : 0;
                const uint4* sc = reinterpret_cast<const uint4*>(w1 + (size_t)(32 * r + 8 * (l2 / 7)) * F_ + 224 * f + 56 * (warp - 12)) + (l2 % 7);
#pragma unroll
                for (int z = 0; z < 8; z++) ev_[z] = __ldg(sc + z * (F_ / 8));
            }
            {
                uint32_t b;
                for (unsigned it = 0;; it++) {
                    asm volatile("ld.relaxed.gpu.global.u32 %0, [%1];" : "=r"(b) : "l"(g_stats + 128 * r + (i & 64) + 2 * (i & 31) + ((i >> 5) & 1)) : "memory");
                    if (!__any_sync(0xffffffffu, (b >> 31) ^ par)) break;
                    if (it > 1000000u) __trap();
                    __nanosleep(100);
                }
                const float rs = 0.125f * rcp_a(bf_hi(b & 0x7fffffffu));
                *reinterpret_cast<float2*>(sm + OFF_RS + 8 * i) = make_float2(rs, -512.f * bf_lo(b) * rs);
                *reinterpret_cast<uint32_t*>(sm + OFF_ST + 4 * i) = (b & 0x7fffffffu) ^ 0x8000u;
                asm volatile("mbarrier.arrive.shared::cta.b64 _, [%0];" ::"r"(bR) : "memory");
            }
            if (i == 0) TS(44);
            {
                float cs[8];
#pragma unroll
                for (int z = 0; z < 4; z++) {
                    float lo = 0.f, hi = 0.f;
#pragma unroll
                    for (int y = 0; y < 8; y++) { lo += bf_lo((&ev_[y].x)[z]); hi += bf_hi((&ev_[y].x)[z]); }
                    cs[2 * z] = lo; cs[2 * z + 1] = hi;
                }
#pragma unroll
                for (int z = 0; z < 8; z++) cs[z] += __shfl_down_sync(0xffffffffu, cs[z], 14);
#pragma unroll
                for (int z = 0; z < 8; z++) cs[z] += __shfl_down_sync(0xffffffffu, cs[z], 7);
                uint32_t* cd = g_colsum + r * 1792 + 224 * f + 56 * (warp - 12) + 8 * lane;
#pragma unroll
                for (int z = 0; z < 2; z++)
                    stg128p(cd + 4 * z, (__float_as_uint(cs[4 * z]) & ~1u) | par, __float_as_uint(cs[4 * z + 1]), (__float_as_uint(cs[4 * z + 2]) & ~1u) | par, __float_as_uint(cs[4 * z + 3]), lane < 7);
            }
            if (i == 0) TS(15);
            uint32_t hx[4];
            wtab_pre(hx, reinterpret_cast<const unsigned short*>(wr), reinterpret_cast<const unsigned short*>(wi), bid, 0, i);
            {
                float ca, cb;
                const int ip = i < 112 ? i : 0;
                const uint32_t bv = __ldg(reinterpret_cast<const uint32_t*>(b1 + 224 * f) + ip);
                for (unsigned it = 0;; it++) {
                    uint2 v[16];
#pragma unroll
                    for (int z = 0; z < 16; z++) v[z] = ldcv2(g_colsum + z * 1792 + 224 * f + 2 * ip);
                    uint32_t bad = 0;
                    ca = 0.f; cb = 0.f;
#pragma unroll
                    for (int z = 0; z < 16; z++) { bad |= v[z].x ^ par; ca += __uint_as_float(v[z].x); cb += __uint_as_float(v[z].y); }
                    if (!__any_sync(0xffffffffu, bad & 1)) break;
                    if (it > 300000u) __trap();
                    __nanosleep(400);
                }
                uint32_t row[8] = {0, 0, 0, bv, 0, 0, 0, 0};
#pragma unroll
                for (int z = 0; z < 3; z++) { row[z] = pack_bf2(ca, cb); ca -= bf_lo(row[z]); cb -= bf_hi(row[z]); }
                const int pc = 2 * i + 32 * (f & 1);
                mbar_wait(bC2, 0);
#pragma unroll
                for (int z = 0; z < 8; z++) sts32p(sb + OFF_BX + (pc >> 6) * 1024 + z * 128 + ((((pc >> 3) & 7) ^ z) << 4) + (pc & 7) * 2, row[z], i < 112);
                asm volatile("fence.proxy.async.shared::cta;" ::: "memory");
                asm volatile("mbarrier.arrive.shared::cta.b64 _, [%0];" ::"r"(bT) : "memory");
            }
            if (i == 0) TS(16);
            mbar_wait(bFF, 0);
            wtab(reinterpret_cast<const unsigned short*>(sm + OFF_WST), reinterpret_cast<const unsigned short*>(sm + OFF_WST + 8752), hx, bid, 0, i);
            FBAR(1);
            if (i == 64) sig_cnt(&g_cntW);
            if (i == 0) TS(63);
        } else {
            asm volatile("setmaxnreg.dec.sync.aligned.u32 120;");
            const int q = 32 * f + (ft >> 2), t = ft & 3;
            float acc[64];
#pragma unroll
            for (int z = 0; z < 64; z++) asm volatile("" : "=f"(acc[z]));
            const int c = (ft >> 3) & 1;
            const float dc = q == 0 ? 1.f : 0.f;
#pragma unroll 1
            for (int hp = 0; hp < 2; hp++) {
                const int hf = hp & 1;
                if (hp == 0) {
                    const int qq = q > 128 ? 512 - q : q;
                    float2 ee[4];
#pragma unroll
                    for (int z = 0; z < 4; z++) ee[z] = cis_neg((qq * (2 * t + (z & 1) + 8 * (z >> 1))) & 511, 1.0f / 512.0f);
                    if (q == 0) { ee[0].y = 1.f; ee[1].y = -1.f; ee[2].y = 1.f; ee[3].y = -1.f; }
                    const float2 rot = cis_neg((qq * 16) & 511, 1.0f / 512.0f);
#pragma unroll 1
                    for (int k = 0; k < 8; k++) {
                        const uint32_t db = mkdlo(sb + k * 16384, 16);
#pragma unroll
                        for (int hh = 0; hh < 2; hh++) {
                            uint32_t A[8];
#pragma unroll
                            for (int kk = 0; kk < 2; kk++) {
                                A[4 * kk] = pack_bf2(ee[0].x, ee[1].x); A[4 * kk + 1] = pack_bf2(ee[0].y, ee[1].y);
                                A[4 * kk + 2] = pack_bf2(ee[2].x, ee[3].x); A[4 * kk + 3] = pack_bf2(ee[2].y, ee[3].y);
#pragma unroll
                                for (int z = 0; z < 4; z++) ee[z] = cmul(ee[z], rot);
                            }
                            if (hh == 0) mbar_wait(bXK + 8 * k, 0);
                            if (hh == 0 && ft == 32 && k < 5) tma_x(sb, &maps.m[0], k + 3, r, bXK);
                            WG_FENCE();
                            wgmma_dft(acc, A[0], A[1], A[2], A[3], db + 4 * hh, (k | hh) != 0);
                            wgmma_dft(acc, A[4], A[5], A[6], A[7], db + 4 * hh + 2, 1);
                            WG_COMMIT();
                            WG_WAIT(1);
                        }
                        if (k == 3 && lane == 0) asm volatile("mbarrier.arrive.shared::cta.b64 _, [%0];" ::"r"(bC2) : "memory");
                    }
                    WG_WAIT(0);
                    fence_regs(acc);
                    if (lane == 0) asm volatile("mbarrier.arrive.shared::cta.b64 _, [%0];" ::"r"(bD) : "memory");
                    if (ft == 0) TS(12);
                    mbar_wait(bC0, 0);
                    mbar_wait(bR, 0);
                    ep1 = *reinterpret_cast<volatile unsigned*>(sm + OFF_EP); par = ep1 & 1;
                }
                const uint32_t sbuf = sb + OFF_FFT + hf * 8192;
                uint32_t* Z1 = g_Z1;
                const int on = hp + 1;
                const uint32_t ad = sbuf + (ft >> 5) * 2048 + (lane & 7) * 256 + ((lane >> 3) & 1) * 128;
                const float4* rsp = reinterpret_cast<const float4*>(sm + OFF_RS) + 32 * hf + t;
#pragma unroll
                for (int j2 = 0; j2 < 4; j2++) {
                    uint32_t pk[4];
#pragma unroll
                    for (int y = 0; y < 2; y++) {
                        const int j = 2 * j2 + y;
                        const float4 cc = rsp[4 * j];
                        pk[2 * y] = pack_h2(fmaf(acc[4 * j], cc.x, dc * cc.y), fmaf(acc[4 * j + 1], cc.z, dc * cc.w));
                        pk[2 * y + 1] = pack_h2(acc[4 * j + 2] * cc.x, acc[4 * j + 3] * cc.z);
                    }
                    asm volatile("{\n.reg .pred p;\nsetp.ne.s32 p, %5, 0;\n@p stmatrix.sync.aligned.m8n8.x4.shared.b16 [%0], {%1,%2,%3,%4};\n}"
                                 ::"r"(ad + (((2 * j2 + (lane >> 4)) ^ (lane & 7)) << 4)), "r"(pk[0]), "r"(pk[1]), "r"(pk[2]), "r"(pk[3]), "r"(on) : "memory");
                }
#pragma unroll
                for (int z = 0; z < 32; z++) acc[z] = acc[z + 32];
                asm volatile("bar.sync 10, 128;" ::: "memory");
                const int n2 = 2 * r + hf;
                const int gch = ((ft ^ (ft >> 4) ^ n2) & 7) * 4;
                uint32_t* dst = Z1 + (32 * f + (ft >> 4)) * 2048 + (32 * c + n2) * 32 + gch;
#pragma unroll
                for (int it = 0; it < 4; it++) {
                    uint4 v;
                    asm volatile("ld.shared.v4.u32 {%0,%1,%2,%3}, [%4];" : "=r"(v.x), "=r"(v.y), "=r"(v.z), "=r"(v.w) : "r"(sbuf + it * 2048 + ft * 16));
                    v.x = (v.x & ~1u) | par;
                    uint32_t* d2 = dst + it * 8 * 2048;
                    if (it == 0) {
                        const uint32_t sg = c ? NEG2 : 0u, km = f ? ~0u : 0u;
                        stg128p(Z1 + (f ? 257 * 2048 + 32 * c * 32 : c * 256 * 2048 + 32 * 32) + n2 * 32 + gch, f ? v.x ^ sg : par, (v.y ^ sg) & km, (v.z ^ sg) & km, (v.w ^ sg) & km,
                                on && ft < 16 && (f & 3) == 0);
                        if (f == 0 && ft < 16) d2 = Z1 + c * 256 * 2048 + n2 * 32 + gch;
                    }
                    stg128p(d2, v.x, v.y, v.z, v.w, on);
                }
            }
            if (ft == 0) TS(1);
            asm volatile("setmaxnreg.dec.sync.aligned.u32 104;");
            uint32_t hx[4];
            wtab_pre(hx, reinterpret_cast<const unsigned short*>(wr), reinterpret_cast<const unsigned short*>(wi), bid, 1, ft);
            mbar_wait(bFF, 0);
            if (ft == 0) TS(27);
            wtab(reinterpret_cast<const unsigned short*>(sm + OFF_WST), reinterpret_cast<const unsigned short*>(sm + OFF_WST + 8752), hx, bid, 1, ft);
            asm volatile("bar.sync 10, 128;" ::: "memory");
            if (ft == 64) sig_cnt(&g_cntW);
            if (ft == 0) TS(9);
        }
        const uint32_t buf = sb + OFF_FFT;
        uint32_t Cs[4], Ns[4];
        dft32_seeds(Cs, Ns, ft);
#pragma unroll 1
        for (int si = 0; si < 6; si++) {
            const int st = si ? si : 5;
            int fo = ft; OPAQUE(fo);
            float acc[32];
            if (st == 5 && !wgi) {
                const int kb = bid == 0 ? 256 : bid == 128 ? 257 : 256 - bid;
                const uint4* z2 = reinterpret_cast<const uint4*>(g_Z2 + (4 * n2r + (jb >> 4)) * 4096);
                ll_fetch(si ? z2 : reinterpret_cast<const uint4*>(g_Z1 + bid * 2048), si ? z2 + 512 : reinterpret_cast<const uint4*>(g_Z1 + kb * 2048),
                         si ? buf + (fo & 1) * 8192 + (fo >> 4) * 128 + ((((fo >> 1) ^ (fo >> 4)) & 7) << 4) : buf + fo * 16, si ? 1024 : 2048, par, si >> 2, fo);
                if (ft == 0) TS(si ? 4 : 2);
                if (bid == 0 && fo == 0 && si) *(volatile unsigned*)&g_epoch = ep1;
                if (!si) continue;
            }
            if (si == 5 && warp == 12) {
                const uint4* gp = g_part + (r * 8 + f) * 8192;
                mbar_wait(bC0, 1);
                fetch_parts(sb, gp, 2, f, lane);
                const uint4* pp = gp + ((lane & 7) == f ? f ^ 1 : lane & 7) * 1024 + 1023;
                asm volatile("{\n.reg .pred p;\n.reg .u32 n, v;\nmov.u32 n, 0;\n"
                             "W_%=:\nld.relaxed.gpu.global.u32 v, [%0];\nxor.b32 v, v, %1;\nand.b32 v, v, 1;\nsetp.eq.u32 p, v, 0;\n"
                             "vote.sync.all.pred p, p, 0xffffffff;\n@p bra.uni D_%=;\n"
                             "nanosleep.u32 100;\nadd.u32 n, n, 1;\nsetp.lt.u32 p, n, 4000000;\n@p bra.uni W_%=;\ntrap;\nD_%=:\n}" ::"l"(pp), "r"(par) : "memory");
                fetch_parts(sb, gp, 3, f, lane);
            }
            if (si) {
                if (si == 2 && fo == 128) {
                    wait_cnt(&g_cntW, ep1 * 256u);
                    asm volatile("fence.proxy.async.global;" ::: "memory");
                    mbar_expect_tx(bX, 17408);
                    asm volatile("cp.async.bulk.shared::cluster.global.mbarrier::complete_tx::bytes [%0], [%1], 1024, [%2];" ::"r"(sb + OFF_WST + 16384), "l"(b2), "r"(bX) : "memory");
                    asm volatile("cp.async.bulk.shared::cluster.global.mbarrier::complete_tx::bytes [%0], [%1], 16384, [%2];" ::"r"(sb + OFF_WST), "l"(g_WT + bid * 4096), "r"(bX) : "memory");
                }
                asm volatile("fence.proxy.async.shared::cta;" ::: "memory");
                FFT_BAR();
                uint32_t bw = buf + wgi * 8192; OPAQUE(bw);
                dft32_stage<true>(acc, Cs, Ns, __shfl_sync(0xffffffffu, bw, 0), st & 1);
                if (ft == 0) TS(46 + 2 * si);
                asm volatile("bar.arrive %0, 256;" ::"r"(13 - wgi) : "memory");
                if (ft == 0) TS(28 + (st & 3));
            } else {
#pragma unroll
                for (int z = 0; z < 32; z++) asm volatile("" : "=f"(acc[z]));
            }
            if (st == 5) {
                postC(acc, buf, si, si ? 12 + wgi : 0, fo);
                if (ft == 128 && !si) TS(58);
            } else if (st == 2) {
                mbar_wait(bX, 0);
                post2(acc, bid, sb + OFF_WST, buf, 12 + wgi, fo);
            } else if (st == 4) {
                post4(acc, bid, par, fo);
                WSYNC(12 + wgi);
                if (ft == 0) TS(3);
                if (extra) return;
            } else {
                post13(acc, st >> 1, buf, 12 + wgi, fo);
            }
            if (ft == 0) TS(47 + 2 * si);
        }
        if (ft == 0) TS(5);
        uint4 xq[2];
        load_x(xq, x, rowb, tid);
        combine<1>(sb, xq, out, rowb, tid);
    } else {
        if (extra) return;
        asm volatile("setmaxnreg.inc.sync.aligned.u32 144;");
        const int wg = warp >> 2, wt = tid & 127;
        float accA[96], accB[16];
        uint32_t da = __reduce_or_sync(0xffffffffu, (((sb + wg * 8192) & 0x3FFFF) >> 4) | (1u << 16));
        const uint32_t dba0 = __reduce_or_sync(0xffffffffu, ((((sb + OFF_W1) & 0x3FFFF) >> 4) | (512u << 16)) + ((f & 1) ? 512 : 0));
        const uint32_t dbd = (f & 1) ? (uint32_t)(4 - 512) : 1536u;
        uint32_t dba = dba0;
#pragma unroll 1
        for (int k = 0; k < 8; k++) {
            if (k == 0 && tid == 0) TS(61);
            mbar_wait(bXK + 8 * k, 0);
            mbar_wait(bFULL + 8 * k, 0);
            if (k == 0 && tid == 0) TS(10);
            if (k == 2 && tid == 160) asm volatile("cp.async.bulk.prefetch.L2.global [%0], %1;" ::"l"(w2 + (size_t)bid * 14 * 512), "r"(14 * 1024) : "memory");
            const uint32_t dbb = dba + dbd;
            WG_FENCE();
#pragma unroll
            for (int kk = 0; kk < 4; kk++) {
                wgmma_ss_n192(accA, da + 2 * kk, dba + 128 * kk, (k | kk) != 0);
                wgmma_ss_n32(accB, da + 2 * kk, dbb + 128 * kk, (k | kk) != 0);
            }
            WG_COMMIT();
            da += 1024; dba = dba == dba0 + 2 * (W1SLOT >> 4) ? dba0 : dba + (W1SLOT >> 4);
            WG_WAIT(1);
            if (lane == 0 && (k == 1 || k == 3)) asm volatile("mbarrier.arrive.shared::cta.b64 _, [%0];" ::"r"(k == 1 ? bC0 : bC2) : "memory");
            if (k == 3 && tid == 64) {
                mbar_wait(bC2, 0);
                const uint32_t n = bid == 127 ? 8224 : 8752;
                mbar_expect_tx(bFF, 2 * 8752);
                if (bid == 127) {
                    asm volatile("cp.async.bulk.shared::cluster.global.mbarrier::complete_tx::bytes [%0], [%1], 528, [%2];" ::"r"(sb + OFF_WST + 8224), "l"(wr), "r"(bFF) : "memory");
                    asm volatile("cp.async.bulk.shared::cluster.global.mbarrier::complete_tx::bytes [%0], [%1], 528, [%2];" ::"r"(sb + OFF_WST + 8752 + 8224), "l"(wi), "r"(bFF) : "memory");
                }
                asm volatile("cp.async.bulk.shared::cluster.global.mbarrier::complete_tx::bytes [%0], [%1], %2, [%3];" ::"r"(sb + OFF_WST), "l"(wr + (size_t)bid * 4112), "r"(n), "r"(bFF) : "memory");
                asm volatile("cp.async.bulk.shared::cluster.global.mbarrier::complete_tx::bytes [%0], [%1], %2, [%3];" ::"r"(sb + OFF_WST + 8752), "l"(wi + (size_t)bid * 4112), "r"(n), "r"(bFF) : "memory");
            }
            if (wt == 32 && k > 0 && k < 6) release(sb, &maps, k + 2, f);
        }
        WG_WAIT(0);
        fence_regs(accA); fence_regs(accB);
        asm volatile("setmaxnreg.inc.sync.aligned.u32 152;");
        {
            mbar_wait(bT, 0);
            const uint32_t q0 = reinterpret_cast<const uint32_t*>(sm + OFF_ST)[16 * warp + (lane >> 2)], q1 = reinterpret_cast<const uint32_t*>(sm + OFF_ST)[16 * warp + (lane >> 2) + 8];
            const uint32_t sel = (lane & 3) == 0 ? 0x1010u : (lane & 3) == 1 ? 0x3210u : 0x4444u;
            const uint32_t a0 = __byte_perm(q0, 0, sel), a1 = __byte_perm(q1, 0, sel);
            const uint64_t db = mkdesc(sb + OFF_BX, 1024, 0, 1);
            WG_FENCE();
            const uint64_t dba = db + ((f & 1) ? 64 : 0);
            wgmma_rs_n192(accA, a0, a1, 0u, 0u, dba, 1);
            wgmma_rs_n32(accB, a0, a1, 0u, 0u, db + ((f & 1) ? 4 : 192), 1);
            WG_COMMIT();
        }
        WG_WAIT(0);
        fence_regs(accA); fence_regs(accB);
        if (wt == 32) release(sb, &maps, 9, f);
        asm volatile("bar.sync 3, 256;" ::: "memory");
        mbar_wait(bD, 0);
        const unsigned par = *reinterpret_cast<volatile unsigned*>(sm + OFF_EP) & 1;
        if (tid == 0) { *reinterpret_cast<volatile unsigned*>(sm + OFF_CNT + 60) = 1; TS(11); }
        const int g = lane >> 2, t = lane & 3;
        uint32_t h[56];
        {
            const float r0 = 4.f * reinterpret_cast<const float2*>(sm + OFF_RS)[16 * warp + g].x, r1 = 4.f * reinterpret_cast<const float2*>(sm + OFF_RS)[16 * warp + g + 8].x;
            uint32_t hp = sb + OFF_H + tid * 8;
#pragma unroll 1
            for (int i = 0; i < 2; i++) {
#pragma unroll
                for (int z = 0; z < 14; z++) {
                    const float v0 = gelu_h(accA[4 * z + 0] * r0), v1 = gelu_h(accA[4 * z + 1] * r0);
                    const float v2 = gelu_h(accA[4 * z + 2] * r1), v3 = gelu_h(accA[4 * z + 3] * r1);
                    asm volatile("st.shared.v2.u32 [%0], {%1,%2};" ::"r"(hp + z * 2048), "r"(pack_bf2(v0, v1)), "r"(pack_bf2(v2, v3)) : "memory");
                }
                hp += 14 * 2048;
#pragma unroll
                for (int z = 0; z < 40; z++) accA[z] = accA[z + 56];
#pragma unroll
                for (int z = 0; z < 16; z++) accA[40 + z] = accB[z];
            }
        }
#pragma unroll
        for (int jn = 0; jn < 28; jn++)
            asm volatile("ld.shared.v2.u32 {%0,%1}, [%2];" : "=r"(h[2 * jn]), "=r"(h[2 * jn + 1]) : "r"(sb + OFF_H + tid * 8 + jn * 2048 + (f & 1) * (jn < 4 ? 49152 : -8192)) : "memory");
        {
            uint32_t z = 0;
#pragma unroll
            for (int i = 0; i < 56; i += 8) z ^= h[i];
            asm volatile("" ::"r"(z) : "memory");
            asm volatile("mbarrier.arrive.shared::cta.b64 _, [%0];" ::"r"(bXF) : "memory");
            asm volatile("bar.sync 3, 256;" ::: "memory");
        }
        if (tid == 0) TS(13);
        uint4* pdst = g_part + (r * 8 + 4 * wg + 2 * (warp & 1) + ((warp >> 1) & 1)) * 8192 + f * 1024 + lane;
        const bool mine = 4 * wg + 2 * (warp & 1) + ((warp >> 1) & 1) == f;
        if (wg) asm volatile("bar.arrive 7, 256;" ::: "memory");
        const uint4* gp = g_part + (r * 8 + f) * 8192;
#pragma unroll 1
        for (int sl = 0; sl < 4; sl++) {
            float acc[64];
            mbar_wait(bFULL + 8 * (8 + sl), 0);
            const uint32_t db = mkdlo(sb + OFF_W2 + (sl & 1) * 57344, 28672);
            if (wg) asm volatile("bar.sync 8, 256;" ::: "memory"); else asm volatile("bar.sync 7, 256;" ::: "memory");
            WG_FENCE();
#pragma unroll
            for (int kk = 0; kk < 14; kk++) wgmma_rs_n128(acc, h[4 * kk], h[4 * kk + 1], h[4 * kk + 2], h[4 * kk + 3], db + 128 * kk, kk != 0);
            WG_COMMIT();
            if (!wg) asm volatile("bar.arrive 8, 256;" ::: "memory"); else if (sl < 3) asm volatile("bar.arrive 7, 256;" ::: "memory");
            WG_WAIT(0);
            fence_regs(acc);
            if (tid == 0) TS(18 + 2 * sl);
            if (wt == 32 && sl < 2) release(sb, &maps, 10 + sl, f);
            if (sl == 3 && lane == 0) asm volatile("mbarrier.arrive.shared::cta.b64 _, [%0];" ::"r"(bC0) : "memory");
            ship_out(acc, pdst + sl * 256, mine ? sb + lane * 16 + (sl < 2 ? OFF_RECV + sl * 32768 + f * 4096 : OFF_OWN + (sl - 2) * 4096) : 0u, par);
            if (sl >= FD && sl < FD + 2 && warp == 7) fetch_parts(sb, gp, sl - FD, f, lane);
            if (tid == 0) TS(19 + 2 * sl);
        }
        if (tid == 0) TS(14);
        asm volatile("bar.sync 3, 256;" ::: "memory");
        mbar_wait(bX, 0);
        if (tid == 0) TS(6);
        uint4 xq[2];
        load_x(xq, x, rowb, tid);
#pragma unroll 1
        for (int bk = 0; bk < 4; bk++) {
            int to = tid; OPAQUE(to);
            const int rho = ((to >> 2) & 7) + ((to >> 3) & 8);
            const uint32_t so = sb + (bk < 2 ? OFF_RECV : OFF_W2) + (bk & 1) * 32768 + to * 16;
            uint4 v[8];
            mbar_wait(bG + 8 * bk, 0);
            if (tid == 32) TS(40 + bk);
            uint32_t bad = 0;
#pragma unroll
            for (int i = 0; i < 8; i++) {
                asm volatile("ld.shared.v4.u32 {%0,%1,%2,%3}, [%4];" : "=r"(v[i].x), "=r"(v[i].y), "=r"(v[i].z), "=r"(v[i].w) : "r"(i == f && bk >= 2 ? sb + OFF_OWN + (bk - 2) * 4096 + to * 16 : so + i * 4096));
                bad |= v[i].x ^ par;
            }
            if (bad & 1) {
#pragma unroll
                for (int i = 0; i < 8; i++)
                    asm volatile("{\n.reg .pred p;\n.reg .u32 n, a;\nmov.u32 n, 0;\n"
                                 "W_%=:\nxor.b32 a, %0, %5;\nand.b32 a, a, 1;\nsetp.eq.u32 p, a, 0;\n@p bra D_%=;\n"
                                 "ld.relaxed.gpu.global.v4.u32 {%0,%1,%2,%3}, [%4];\nadd.u32 n, n, 1;\nsetp.lt.u32 p, n, 4000000;\n@p bra W_%=;\ntrap;\nD_%=:\n}"
                                 : "+r"(v[i].x), "+r"(v[i].y), "+r"(v[i].z), "+r"(v[i].w) : "l"(gp + i * 1024 + bk * 256 + to), "r"(par) : "memory");
            }
            if (tid == 32) TS(32 + bk);
            const uint32_t wo = (2 * bk + (to >> 7)) * 128 + ((to >> 5) & 1) * 64 + (to & 3) * 4;
#pragma unroll
            for (int z = 0; z < 4; z++) {
                const uint32_t bv = *reinterpret_cast<const uint32_t*>(sm + OFF_WST + 16384 + wo + 16 * z);
                float y0 = bf_lo(bv), y1 = bf_hi(bv);
#pragma unroll
                for (int i = 0; i < 8; i++) { const uint32_t w = (&v[i].x)[z]; y0 += bf_lo(w); y1 += bf_hi(w); }
                const float h0 = 0.5f * y0, h1 = 0.5f * y1;
                float t0, t1;
                asm("tanh.approx.f32 %0, %1;" : "=f"(t0) : "f"(h0)); asm("tanh.approx.f32 %0, %1;" : "=f"(t1) : "f"(h1));
                sts32(sb + OFF_G + rho * 1024 + wo + 16 * z, pack_bf2(fmaf(h0, t0, h0), fmaf(h1, t1, h1)));
            }
        }
        if (tid == 0) TS(45);
        combine<0>(sb, xq, out, rowb, tid);
        if (tid == 0) TS(8);
    }
}

typedef CUresult (*EncFn)(CUtensorMap*, CUtensorMapDataType, cuuint32_t, void*, const cuuint64_t*, const cuuint64_t*, const cuuint32_t*, const cuuint32_t*,
                          CUtensorMapInterleave, CUtensorMapSwizzle, CUtensorMapL2promotion, CUtensorMapFloatOOBfill);

static void make_map(EncFn enc, CUtensorMap* tm, void* ptr, cuuint64_t d0, cuuint64_t d1, cuuint64_t d2, cuuint64_t s1, cuuint64_t s2,
                     cuuint32_t b0, cuuint32_t b1, cuuint32_t b2, CUtensorMapSwizzle sw) {
    cuuint64_t gd[3] = {d0, d1, d2}, gs[2] = {s1, s2};
    cuuint32_t bd[3] = {b0, b1, b2}, es[3] = {1, 1, 1};
    enc(tm, CU_TENSOR_MAP_DATA_TYPE_BFLOAT16, 3, ptr, gd, gs, bd, es, CU_TENSOR_MAP_INTERLEAVE_NONE, sw,
        CU_TENSOR_MAP_L2_PROMOTION_L2_128B, CU_TENSOR_MAP_FLOAT_OOB_FILL_NONE);
}

extern "C" void kernel_launch(void* const* d_in, const int* in_sizes, int n_in, void* d_out, int out_size) {
    static EncFn enc = nullptr;
    if (!enc) {
        void* fn = nullptr; cudaDriverEntryPointQueryResult qr;
        cudaGetDriverEntryPoint("cuTensorMapEncodeTiled", &fn, cudaEnableDefault, &qr);
        enc = (EncFn)fn;
        cudaFuncSetAttribute(fused_kernel, cudaFuncAttributeMaxDynamicSharedMemorySize, SMEM_BYTES);
    }
    void* x = d_in[0]; void* w1 = d_in[4]; void* w2 = d_in[6];
    Maps mp;
    {
        cuuint64_t gd[4] = {512, 32, 2, 32}, gs[3] = {2048, 1024, 65536};
        cuuint32_t bd[4] = {64, 32, 2, 2}, es[4] = {1, 1, 1, 1};
        enc(&mp.m[0], CU_TENSOR_MAP_DATA_TYPE_BFLOAT16, 4, x, gd, gs, bd, es, CU_TENSOR_MAP_INTERLEAVE_NONE, CU_TENSOR_MAP_SWIZZLE_128B,
            CU_TENSOR_MAP_L2_PROMOTION_L2_128B, CU_TENSOR_MAP_FLOAT_OOB_FILL_NONE);
    }
    make_map(enc, &mp.m[1], w1, 64, 512, 28, 3584, 128, 64, 64, 4, CU_TENSOR_MAP_SWIZZLE_128B);
    make_map(enc, &mp.m[2], w2, 64, 1792, 8, 1024, 128, 64, 224, 2, CU_TENSOR_MAP_SWIZZLE_128B);
    fused_kernel<<<129, NTHREADS, SMEM_BYTES>>>((const __nv_bfloat16*)d_in[0], (const __nv_bfloat16*)d_in[1], (const __nv_bfloat16*)d_in[2],
                                                (const __nv_bfloat16*)d_in[4], (const __nv_bfloat16*)d_in[5], (const __nv_bfloat16*)d_in[6],
                                                (const __nv_bfloat16*)d_in[7], (__nv_bfloat16*)d_out, mp);
}
```
